```python
import torch

def _softmax(x, axis=-1):
    return torch.softmax(x, dim=axis)
def _gelu(x):
    return torch.nn.functional.gelu(x, approximate="tanh")
def _silu(x):
    return torch.nn.functional.silu(x)
def _sigmoid(x):
    return torch.sigmoid(x)
def _layernorm(x, axis=-1, eps=1e-5):
    m = x.mean(dim=axis, keepdim=True)
    v = x.var(dim=axis, keepdim=True, unbiased=False)
    return (x - m) / torch.sqrt(v + eps)
def _scatter_add(tgt, idx, src, axis=0):
    return tgt.clone().index_add_(axis, idx, src)
def _segment_sum(src, seg, n):
    out = torch.zeros((n,) + src.shape[1:], dtype=src.dtype)
    return out.index_add_(0, seg, src)
def _pad(x, pw):
    flat = tuple(v for pair in reversed(pw) for v in pair)
    return torch.nn.functional.pad(x, flat)

kernel_name = 'parallel_sum__ssm_conv_s4__mixer_token_mlp__prompt'

def setup_inputs():

    _w = (lambda a: (lambda t: t.to(torch.bfloat16) if t.is_floating_point() else t)(torch.as_tensor(a)))
    def _A_setup():
        B, L, D, N = 1, 2048, 640, 128
        A_re = -(lambda _x: torch.exp(torch.as_tensor(_x)))((lambda *s: torch.randn(*s, dtype=torch.bfloat16) * 3.2)(D, N))
        A_im = torch.pi * (lambda *s: torch.randn(*s, dtype=torch.bfloat16) * 0.05)(D, N)
        B_re = (lambda *s: torch.randn(*s, dtype=torch.bfloat16) * 0.1)(D, N)
        B_im = (lambda *s: torch.randn(*s, dtype=torch.bfloat16) * 0.1)(D, N)
        C_re = (lambda *s: torch.randn(*s, dtype=torch.bfloat16) * 0.1)(D, N)
        C_im = (lambda *s: torch.randn(*s, dtype=torch.bfloat16) * 0.1)(D, N)
        log_dt = (lambda *s: torch.randn(*s, dtype=torch.bfloat16) * 0.05)(D) * 0.5 - 4.0
        Dskip = (lambda *s: torch.randn(*s, dtype=torch.bfloat16) * 0.05)(D)
        return {
            "u": _w((lambda *s: torch.randn(*s, dtype=torch.bfloat16) * 0.05)(B, L, D)),
            "A_re": _w(A_re),
            "A_im": _w(A_im),
            "B_re": _w(B_re),
            "B_im": _w(B_im),
            "C_re": _w(C_re),
            "C_im": _w(C_im),
            "log_dt": _w(log_dt),
            "Dskip": _w(Dskip),
        }
    _A_in = _A_setup()

    def _B_setup():
        B, S, D, F = 1, 2048, 640, 1728
        return {
            "x": _w((lambda *s: torch.randn(*s, dtype=torch.bfloat16) * 0.05)(B, S, D)),
            "w1": _w((lambda *s: torch.randn(*s, dtype=torch.bfloat16) * 0.8)(S, F) * (S ** -0.5)),
            "b1": _w((lambda *s: torch.randn(*s, dtype=torch.bfloat16) * 3.2)(F) * 0.02),
            "w2": _w((lambda *s: torch.randn(*s, dtype=torch.bfloat16) * 0.8)(F, S) * (F ** -0.5)),
            "b2": _w((lambda *s: torch.randn(*s, dtype=torch.bfloat16) * 3.2)(S) * 0.02),
        }
    _B_in = _B_setup()

    return {
        "A_u": _A_in["u"],
        "A_A_re": _A_in["A_re"],
        "A_A_im": _A_in["A_im"],
        "A_B_re": _A_in["B_re"],
        "A_B_im": _A_in["B_im"],
        "A_C_re": _A_in["C_re"],
        "A_C_im": _A_in["C_im"],
        "A_log_dt": _A_in["log_dt"],
        "A_Dskip": _A_in["Dskip"],
        "B_x": _B_in["x"],
        "B_w1": _B_in["w1"],
        "B_b1": _B_in["b1"],
        "B_w2": _B_in["w2"],
        "B_b2": _B_in["b2"],
    }

def reference(A_u, A_A_re, A_A_im, A_B_re, A_B_im, A_C_re, A_C_im, A_log_dt, A_Dskip, B_x, B_w1, B_b1, B_w2, B_b2):
    def _A_ref(u, A_re, A_im, B_re, B_im, C_re, C_im, log_dt, Dskip):
        Bsz, L, D = u.shape
        dt = torch.exp(log_dt)[:, None]
        A = A_re + 1j * A_im
        Bc = B_re + 1j * B_im
        Cc = C_re + 1j * C_im
        logdA = dt * A
        dB = dt * Bc
        l = (lambda x, dt: x.to(dt))(torch.arange(L), A_re.dtype)
        P = torch.exp(logdA[:, :, None] * l[None, None, :])
        K = torch.einsum("dn,dnl,dn->dl", Cc, P, dB).real
        L2 = 2 * L
        Kp = _pad(K, ((0, 0), (0, L)))
        up = (lambda x, *d: x.permute(*d))(u, 0, 2, 1)
        up = _pad(up, ((0, 0), (0, 0), (0, L)))
        Kf = (lambda x, axes=(-2,-1): torch.fft.rfft2(x.float(), dim=axes))(Kp[:, None, :], axes=(-2, -1))
        Uf = (lambda x, axes=(-2,-1): torch.fft.rfft2(x.float(), dim=axes))(up[:, :, None, :], axes=(-2, -1))
        Yf = Uf * Kf[None, :, :, :]
        y = (lambda x, s, axes=(-2,-1): torch.fft.irfft2(x, s=s, dim=axes).to(torch.bfloat16))(Yf, (1, L2), axes=(-2, -1))[:, :, 0, :L]
        y = (lambda x, *d: x.permute(*d))(y, 0, 2, 1) + u * Dskip[None, None, :]
        return y

    def _B_ref(x, w1, b1, w2, b2):
        B, S, D = x.shape
        h = _layernorm(x, axis=-1)
        u = torch.einsum("bsd,sf->bdf", h, w1) + b1
        u = _gelu(u)
        y = torch.einsum("bdf,fs->bds", u, w2) + b2
        return (lambda x, *d: x.permute(*d))(y, 0, 2, 1)

    x = A_u
    xn = _layernorm(x, axis=-1)
    return x + _A_ref(xn, A_A_re, A_A_im, A_B_re, A_B_im, A_C_re, A_C_im, A_log_dt, A_Dskip) + _B_ref(xn, B_w1, B_b1, B_w2, B_b2)
```

```cpp
#include <cuda_runtime.h>
#include <cuda_bf16.h>
#include <cuda.h>
#include <stdint.h>
#include <stdio.h>

namespace {

constexpr int S_ = 2048, D_ = 640, F_ = 1728, NM = 128;
constexpr int NCTA = 132, NTHR = 256;
constexpr int NSLOT = 7, SLOT = 28672, ABYTES = 8192;
constexpr int N_G1 = 108, N_G2 = 128;
constexpr int KTAB = 3200;
constexpr int OFF_BAR = 0;
constexpr int OFF_RED = 256;
constexpr int OFF_EP = 192;
constexpr int OFF_BIAS = 1280;
constexpr int OFF_SLOT = 2048;
constexpr int OFF_X = OFF_SLOT + NSLOT * SLOT;
constexpr int SMEM_BYTES = 232448;
constexpr int B_EMPTY = 7, B_U = 14, B_X = 16, B_Y = 17, B_DUMMY = 18;
constexpr int NB_WG0 = 1, NB_WG1 = 2, NB_G1DONE = 3, NB_CONVDONE = 4, NB_KGEN = 5, NB_RES = 6, NB_GOK = 7, NB_XCH = 8;
constexpr uint32_t SB = 1024;
constexpr int PC = 0, PA = 1136, PB = 1768, PF = 2144, TX = 2520;
constexpr int SPIN_LIMIT = 1 << 20;

__device__ __align__(1024) __nv_bfloat16 g_uh[2 * D_ * S_];
__device__ __align__(1024) __nv_bfloat16 g_G[D_ * F_];
__device__ __align__(1024) __nv_bfloat16 g_y[D_ * S_];
#define NREP 2
constexpr int CSTRIDE = 1056, C_H = 0, C_G = CSTRIDE, C_TG = C_G + 4, C_S = 2 * CSTRIDE, C_T = C_S + 2, C_Y = 3 * CSTRIDE, CREP = 4 * CSTRIDE;
__device__ __align__(128) unsigned g_cnt[NREP * CREP];
#define XDELAY 300
#define WEARLY 1
#define GATE2 200
#define GATE1 400
#define PROMO CU_TENSOR_MAP_L2_PROMOTION_L2_128B
#define PFN 3
#define STAMPW(wp, i) do { } while (0)
#define STAMPG(wp, i) do { } while (0)
#define STAMPINIT() do { } while (0)
#define STAMPDUMP() do { } while (0)

struct Params {
    const char* base;
    int off[8];
    const __nv_bfloat16 *x, *b1, *b2;
    __nv_bfloat16 *out, *uh, *G, *y;
    unsigned* cnt;
    uint32_t zero;
};

__device__ __forceinline__ void wg_fence() { asm volatile("wgmma.fence.sync.aligned;" ::: "memory"); }
__device__ __forceinline__ void wg_commit() { asm volatile("wgmma.commit_group.sync.aligned;" ::: "memory"); }
template <int N> __device__ __forceinline__ void wg_wait() { asm volatile("wgmma.wait_group.sync.aligned %0;" :: "n"(N) : "memory"); }
__device__ __forceinline__ void wgmma_n160(float* d, uint64_t da, uint64_t db) {
    asm volatile(
        "wgmma.mma_async.sync.aligned.m64n160k16.f32.bf16.bf16 "
        "{%0,%1,%2,%3,%4,%5,%6,%7,%8,%9,%10,%11,%12,%13,%14,%15,%16,%17,%18,%19,"
        "%20,%21,%22,%23,%24,%25,%26,%27,%28,%29,%30,%31,%32,%33,%34,%35,%36,%37,%38,%39,"
        "%40,%41,%42,%43,%44,%45,%46,%47,%48,%49,%50,%51,%52,%53,%54,%55,%56,%57,%58,%59,"
        "%60,%61,%62,%63,%64,%65,%66,%67,%68,%69,%70,%71,%72,%73,%74,%75,%76,%77,%78,%79}, "
        "%80, %81, 1, 1, 1, 1, 0;"
        : "+f"(d[0]), "+f"(d[1]), "+f"(d[2]), "+f"(d[3]), "+f"(d[4]), "+f"(d[5]), "+f"(d[6]), "+f"(d[7]), "+f"(d[8]), "+f"(d[9]),
          "+f"(d[10]), "+f"(d[11]), "+f"(d[12]), "+f"(d[13]), "+f"(d[14]), "+f"(d[15]), "+f"(d[16]), "+f"(d[17]), "+f"(d[18]), "+f"(d[19]),
          "+f"(d[20]), "+f"(d[21]), "+f"(d[22]), "+f"(d[23]), "+f"(d[24]), "+f"(d[25]), "+f"(d[26]), "+f"(d[27]), "+f"(d[28]), "+f"(d[29]),
          "+f"(d[30]), "+f"(d[31]), "+f"(d[32]), "+f"(d[33]), "+f"(d[34]), "+f"(d[35]), "+f"(d[36]), "+f"(d[37]), "+f"(d[38]), "+f"(d[39]),
          "+f"(d[40]), "+f"(d[41]), "+f"(d[42]), "+f"(d[43]), "+f"(d[44]), "+f"(d[45]), "+f"(d[46]), "+f"(d[47]), "+f"(d[48]), "+f"(d[49]),
          "+f"(d[50]), "+f"(d[51]), "+f"(d[52]), "+f"(d[53]), "+f"(d[54]), "+f"(d[55]), "+f"(d[56]), "+f"(d[57]), "+f"(d[58]), "+f"(d[59]),
          "+f"(d[60]), "+f"(d[61]), "+f"(d[62]), "+f"(d[63]), "+f"(d[64]), "+f"(d[65]), "+f"(d[66]), "+f"(d[67]), "+f"(d[68]), "+f"(d[69]),
          "+f"(d[70]), "+f"(d[71]), "+f"(d[72]), "+f"(d[73]), "+f"(d[74]), "+f"(d[75]), "+f"(d[76]), "+f"(d[77]), "+f"(d[78]), "+f"(d[79])
        : "l"(da), "l"(db));
}
__device__ __forceinline__ void mbar_init(uint32_t bar, uint32_t cnt) { asm volatile("mbarrier.init.shared::cta.b64 [%0], %1;" :: "r"(bar), "r"(cnt) : "memory"); }
__device__ __forceinline__ void mbar_expect_tx(uint32_t bar, uint32_t bytes) { asm volatile("mbarrier.arrive.expect_tx.shared::cta.b64 _, [%0], %1;" :: "r"(bar), "r"(bytes) : "memory"); }
__device__ __forceinline__ void mbar_arrive(uint32_t bar) { asm volatile("mbarrier.arrive.shared::cta.b64 _, [%0];" :: "r"(bar) : "memory"); }
__device__ __forceinline__ bool mbar_try(uint32_t bar, uint32_t parity) {
    uint32_t ok;
    asm volatile("{\n.reg .pred p;\nmbarrier.try_wait.parity.shared::cta.b64 p, [%1], %2;\nselp.u32 %0, 1, 0, p;\n}" : "=r"(ok) : "r"(bar), "r"(parity) : "memory");
    return ok;
}
__device__ __forceinline__ void mbar_wait(uint32_t bar, uint32_t parity) {
    if (__builtin_expect(!mbar_try(bar, parity), 0)) {
        int it = 0;
#pragma unroll 1
        while (!mbar_try(bar, parity)) if (++it > SPIN_LIMIT) __trap();
    }
}
__device__ __forceinline__ void tma2d(uint32_t dst, const CUtensorMap* m, int c0, int c1, uint32_t bar) {
    asm volatile("cp.async.bulk.tensor.2d.shared::cluster.global.mbarrier::complete_tx::bytes [%0], [%1, {%3, %4}], [%2];"
        :: "r"(dst), "l"(m), "r"(bar), "r"(c0), "r"(c1) : "memory");
}
__device__ __forceinline__ void tma3d(uint32_t dst, const CUtensorMap* m, int c0, int c1, int c2, uint32_t bar) {
    asm volatile("cp.async.bulk.tensor.3d.shared::cluster.global.mbarrier::complete_tx::bytes [%0], [%1, {%3, %4, %5}], [%2];"
        :: "r"(dst), "l"(m), "r"(bar), "r"(c0), "r"(c1), "r"(c2) : "memory");
}
__device__ __forceinline__ void tma4d(uint32_t dst, const CUtensorMap* m, int c2, int c3, uint32_t bar) {
    asm volatile("cp.async.bulk.tensor.4d.shared::cluster.global.mbarrier::complete_tx::bytes [%0], [%1, {%4, %4, %5, %3}], [%2];"
        :: "r"(dst), "l"(m), "r"(bar), "r"(c3), "r"(0), "r"(c2) : "memory");
}
__device__ __forceinline__ void pf3d(const CUtensorMap* m, int c0, int c1, int c2) {
    asm volatile("cp.async.bulk.prefetch.tensor.3d.L2.global [%0, {%1, %2, %3}];" :: "l"(m), "r"(c0), "r"(c1), "r"(c2) : "memory");
}
__device__ __forceinline__ void fence_async_global() { asm volatile("fence.proxy.async.global;" ::: "memory"); }
__device__ __forceinline__ void fence_async_smem() { asm volatile("fence.proxy.async.shared::cta;" ::: "memory"); }
__device__ __forceinline__ void bar_sync(int id, int n) { asm volatile("bar.sync %0, %1;" :: "r"(id), "r"(n) : "memory"); }
__device__ __forceinline__ void bar_arrive(int id, int n) { asm volatile("bar.arrive %0, %1;" :: "r"(id), "r"(n) : "memory"); }
__device__ __forceinline__ unsigned long long gtime() { unsigned long long t; asm volatile("mov.u64 %0, %%globaltimer;" : "=l"(t) :: "memory"); return t; }
__device__ __forceinline__ int laneid() { int l; asm volatile("mov.u32 %0, %%laneid;" : "=r"(l)); return l; }
__device__ __forceinline__ bool elect() {
    uint32_t el; asm volatile("{\n.reg .pred p;\nelect.sync _|p, 0xffffffff;\nselp.u32 %0, 1, 0, p;\n}" : "=r"(el)); return el;
}
__device__ __forceinline__ unsigned ld_relaxed(const unsigned* p) { unsigned v; asm volatile("ld.relaxed.gpu.global.u32 %0, [%1];" : "=r"(v) : "l"(p) : "memory"); return v; }
template <bool REL> __device__ __forceinline__ void publish(unsigned* p, int lane) {
    if (lane < NREP) {
        if (REL) asm volatile("red.release.gpu.global.add.u32 [%0], 1;" :: "l"(p + CREP * lane) : "memory");
        else asm volatile("red.relaxed.gpu.global.add.u32 [%0], 1;" :: "l"(p + CREP * lane) : "memory");
    }
    __syncwarp();
}
__device__ __forceinline__ void mma(float* d, uint32_t a0, uint32_t a1, uint32_t a2, uint32_t a3, uint32_t b0, uint32_t b1) {
    asm("mma.sync.aligned.m16n8k16.row.col.f32.bf16.bf16.f32 {%0,%1,%2,%3}, {%4,%5,%6,%7}, {%8,%9}, {%0,%1,%2,%3};"
        : "+f"(d[0]), "+f"(d[1]), "+f"(d[2]), "+f"(d[3]) : "r"(a0), "r"(a1), "r"(a2), "r"(a3), "r"(b0), "r"(b1));
}
__device__ __forceinline__ void ldsm4v(uint32_t* r, uint32_t a) {
    asm volatile("ldmatrix.sync.aligned.m8n8.x4.shared.b16 {%0,%1,%2,%3}, [%4];" : "=r"(r[0]), "=r"(r[1]), "=r"(r[2]), "=r"(r[3]) : "r"(a) : "memory");
}
__device__ __forceinline__ void ldsm2v(uint32_t* r, uint32_t a) {
    asm volatile("ldmatrix.sync.aligned.m8n8.x2.shared.b16 {%0,%1}, [%2];" : "=r"(r[0]), "=r"(r[1]) : "r"(a) : "memory");
}
__device__ __forceinline__ void ldsm4tv(uint32_t* r, uint32_t a) {
    asm volatile("ldmatrix.sync.aligned.m8n8.x4.trans.shared.b16 {%0,%1,%2,%3}, [%4];" : "=r"(r[0]), "=r"(r[1]), "=r"(r[2]), "=r"(r[3]) : "r"(a) : "memory");
}
__device__ __forceinline__ void sts32(uint32_t a, uint32_t v) { asm volatile("st.shared.b32 [%0], %1;" :: "r"(a), "r"(v) : "memory"); }
__device__ __forceinline__ void sts16(uint32_t a, uint32_t v) { asm volatile("st.shared.u16 [%0], %1;" :: "r"(a), "h"((unsigned short)v) : "memory"); }
__device__ __forceinline__ uint32_t movm(uint32_t a) { uint32_t d; asm volatile("movmatrix.sync.aligned.m8n8.trans.b16 %0, %1;" : "=r"(d) : "r"(a)); return d; }
__device__ __forceinline__ uint32_t pack(float lo, float hi) { uint32_t d; asm("cvt.rn.bf16x2.f32 %0, %1, %2;" : "=r"(d) : "f"(hi), "f"(lo)); return d; }
__device__ __forceinline__ uint32_t packv(float lo, float hi) { uint32_t d; asm volatile("cvt.rn.bf16x2.f32 %0, %1, %2;" : "=r"(d) : "f"(hi), "f"(lo) : "memory"); return d; }
__device__ __forceinline__ uint32_t hadd2(uint32_t a, uint32_t b) { uint32_t d; asm("add.rn.bf16x2 %0, %1, %2;" : "=r"(d) : "r"(a), "r"(b)); return d; }
__device__ __forceinline__ uint32_t hfma2(uint32_t a, uint32_t b, uint32_t c) { uint32_t d; asm("fma.rn.bf16x2 %0, %1, %2, %3;" : "=r"(d) : "r"(a), "r"(b), "r"(c)); return d; }
__device__ __forceinline__ float bflo(uint32_t v) { return __uint_as_float(v << 16); }
__device__ __forceinline__ float rbf(float v) { return __uint_as_float(pack(0.f, v)); }

__device__ __forceinline__ uint32_t prmt(uint32_t a, uint32_t b, uint32_t s) { uint32_t d; asm("prmt.b32 %0, %1, %2, %3;" : "=r"(d) : "r"(a), "r"(b), "r"(s)); return d; }
__device__ __forceinline__ void mmav(float* d, const uint32_t* a, const uint32_t* b, const float* c) {
    asm volatile("mma.sync.aligned.m16n8k16.row.col.f32.bf16.bf16.f32 {%0,%1,%2,%3}, {%4,%5,%6,%7}, {%8,%9}, {%10,%11,%12,%13};"
        : "=f"(d[0]), "=f"(d[1]), "=f"(d[2]), "=f"(d[3])
        : "r"(a[0]), "r"(a[1]), "r"(a[2]), "r"(a[3]), "r"(b[0]), "r"(b[1]), "f"(c[0]), "f"(c[1]), "f"(c[2]), "f"(c[3]));
}
__device__ __forceinline__ void lds64v(uint32_t* r, uint32_t a) { asm volatile("ld.shared.v2.b32 {%0,%1}, [%2];" : "=r"(r[0]), "=r"(r[1]) : "r"(a) : "memory"); }
__device__ __forceinline__ float2 lds64f(uint32_t a) { float2 v; asm volatile("ld.shared.v2.f32 {%0,%1}, [%2];" : "=f"(v.x), "=f"(v.y) : "r"(a) : "memory"); return v; }
__device__ __forceinline__ void sts64f(uint32_t a, float x, float y) { asm volatile("st.shared.v2.f32 [%0], {%1,%2};" :: "r"(a), "f"(x), "f"(y) : "memory"); }
__device__ __forceinline__ uint32_t lds32v(uint32_t a) { uint32_t v; asm volatile("ld.shared.b32 %0, [%1];" : "=r"(v) : "r"(a) : "memory"); return v; }
__device__ __forceinline__ uint32_t lds16v(uint32_t a) { uint32_t v; asm volatile("ld.shared.u16 %0, [%1];" : "=r"(v) : "r"(a) : "memory"); return v; }
__device__ __forceinline__ uint4 lds128v(uint32_t a) { uint4 v; asm volatile("ld.shared.v4.b32 {%0,%1,%2,%3}, [%4];" : "=r"(v.x), "=r"(v.y), "=r"(v.z), "=r"(v.w) : "r"(a) : "memory"); return v; }
__device__ __forceinline__ void sts128(uint32_t a, uint32_t x, uint32_t y, uint32_t z, uint32_t w) { asm volatile("st.shared.v4.b32 [%0], {%1,%2,%3,%4};" :: "r"(a), "r"(x), "r"(y), "r"(z), "r"(w) : "memory"); }
__device__ __forceinline__ void stsm4(uint32_t a, const uint32_t* r) {
    asm volatile("stmatrix.sync.aligned.m8n8.x4.shared.b16 [%0], {%1,%2,%3,%4};" :: "r"(a), "r"(r[0]), "r"(r[1]), "r"(r[2]), "r"(r[3]) : "memory");
}
__device__ __forceinline__ void stsm4t(uint32_t a, const uint32_t* r) {
    asm volatile("stmatrix.sync.aligned.m8n8.x4.trans.shared.b16 [%0], {%1,%2,%3,%4};" :: "r"(a), "r"(r[0]), "r"(r[1]), "r"(r[2]), "r"(r[3]) : "memory");
}

template <int BYTES> __device__ __forceinline__ void bulk_store(void* dst, uint32_t src) {
    asm volatile("cp.async.bulk.global.shared::cta.bulk_group [%0], [%1], %2;" :: "l"(dst), "r"(src), "n"(BYTES) : "memory");
}
__device__ __forceinline__ void bulk_wait() { asm volatile("cp.async.bulk.commit_group;\ncp.async.bulk.wait_group 0;" ::: "memory"); fence_async_global(); }
constexpr int XNOFF = SLOT;
__device__ __forceinline__ void layernorm(const Params& p, uint32_t stg, int blk, int warp, bool el) {
    const int lane = laneid(), g = lane >> 2, c = lane & 3, wg = warp >> 2;
    const uint32_t red = SB + OFF_RED + 8 * g;
    uint32_t so = stg + XNOFF + (160 * (warp & 3) + 96 * wg + lane) * 32 + ((lane & 4) << 2);
    const uint32_t zero = p.zero, one = 0x3F803F80u + zero;
    STAMPW(0, 13);
    uint32_t xa[12], xb[12];
    mbar_wait(SB + OFF_BAR + 8 * B_X, 0);
#pragma unroll
    for (int i = 0; i < 3; i++) {
        const uint32_t a = stg + g * 1280 + (160 * (warp & 3) + 96 * wg + 32 * i + 8 * c) * 2;
        uint4 va = make_uint4(0u, 0u, 0u, 0u), vb = va;
        if (i < 2 || wg == 0) { va = lds128v(a); vb = lds128v(a + 8 * 1280); }
        xa[4 * i] = va.x; xa[4 * i + 1] = va.y; xa[4 * i + 2] = va.z; xa[4 * i + 3] = va.w;
        xb[4 * i] = vb.x; xb[4 * i + 1] = vb.y; xb[4 * i + 2] = vb.z; xb[4 * i + 3] = vb.w;
    }
    STAMPW(0, 18);
    float mean[2], var[2];
    {
        float sm[2][4], q1[2][4], q2[2][4];
#pragma unroll
        for (int i = 0; i < 8; i++) { (&sm[0][0])[i] = 0.f; (&q1[0][0])[i] = 0.f; (&q2[0][0])[i] = 0.f; }
        uint32_t af[24];
        const uint32_t ones[2] = {0x3F803F80u, 0x3F803F80u};
#pragma unroll
        for (int k = 0; k < 12; k++) { af[2 * k] = xa[k] ^ zero; af[2 * k + 1] = xb[k] ^ zero; }
#pragma unroll
        for (int k = 0; k < 6; k++) {
            mmav(q1[k & 1], af + 4 * k, xa + 2 * k, q1[k & 1]);
            mmav(q2[k & 1], af + 4 * k, xb + 2 * k, q2[k & 1]);
            mmav(sm[k & 1], af + 4 * k, ones, sm[k & 1]);
        }
        if (c == (g >> 1)) {
            const float qa = (g & 1) ? q1[0][1] + q1[1][1] : q1[0][0] + q1[1][0];
            const float qb = (g & 1) ? q2[0][3] + q2[1][3] : q2[0][2] + q2[1][2];
            sts64f(red + warp * 128, sm[0][0] + sm[1][0], qa);
            sts64f(red + warp * 128 + 64, sm[0][2] + sm[1][2], qb);
        }
        __syncthreads();
#pragma unroll
        for (int h = 0; h < 2; h++) {
            float2 v[8];
#pragma unroll
            for (int j = 0; j < 8; j++) v[j] = lds64f(red + 64 * h + 128 * j);
            mean[h] = (((v[0].x + v[1].x) + (v[2].x + v[3].x)) + ((v[4].x + v[5].x) + (v[6].x + v[7].x))) * (1.f / D_);
            var[h] = fmaxf((((v[0].y + v[1].y) + (v[2].y + v[3].y)) + ((v[4].y + v[5].y) + (v[6].y + v[7].y))) * (1.f / D_) - mean[h] * mean[h], 0.f);
        }
    }
#pragma unroll 1
    for (int st = 0; st < 2; st++) {
        uint32_t m2[2], rh[2], rl[2];
#pragma unroll
        for (int h = 0; h < 2; h++) {
            float den, rinv;
            asm("sqrt.approx.ftz.f32 %0, %1;" : "=f"(den) : "f"(rbf(rbf(var[h]) + 1e-5f)));
            asm("rcp.approx.ftz.f32 %0, %1;" : "=f"(rinv) : "f"(rbf(den)));
            m2[h] = pack(-mean[h], -mean[h]); rh[h] = pack(rinv, rinv);
            const float lo = rinv - bflo(rh[h]);
            rl[h] = pack(lo, lo);
            mean[h] = (mean[h] + bflo(m2[h])) * rinv; var[h] *= rinv * rinv;
        }
#pragma unroll
        for (int k = 0; k < 12; k++) {
            const uint32_t ta = hfma2(xa[k], one, m2[0]), tb = hfma2(xb[k], one, m2[1]);
            xa[k] = hfma2(ta, rh[0], hfma2(ta, rl[0], zero));
            xb[k] = hfma2(tb, rh[1], hfma2(tb, rl[1], zero));
        }
#pragma unroll
        for (int i = 0; i < 3; i++) if (i < 2 || wg == 0) { stsm4t(so + 1024 * i, xa + 4 * i); stsm4t((so ^ 16) + 1024 * i, xb + 4 * i); }
        fence_async_smem();
        __syncthreads();
        if (warp == 1 && el) bulk_store<20480>(p.uh + st * (D_ * S_) + blk * (D_ * 16), stg + (st ? 0 : XNOFF));
        so -= XNOFF;
    }
    STAMPW(0, 16);
    if (warp == 1) {
        if (el) bulk_wait();
        __syncwarp();
        publish<false>(&p.cnt[C_H + (blk >> 3)], lane);
        STAMPW(1, 17);
    }
}

struct cf { float r, i; };
__device__ __forceinline__ cf cmul(cf a, cf b) { cf o; o.r = fmaf(a.r, b.r, -a.i * b.i); o.i = fmaf(a.r, b.i, a.i * b.r); return o; }
__device__ __forceinline__ cf cmulc(cf a, cf b) { cf o; o.r = fmaf(a.r, b.r, a.i * b.i); o.i = fmaf(a.i, b.r, -a.r * b.i); return o; }
__device__ __forceinline__ cf cpow(float e2, float tn) {
    float mag; asm("ex2.approx.ftz.f32 %0, %1;" : "=f"(mag) : "f"(e2));
    const float t = (tn - rintf(tn)) * 6.283185307179586f;
    cf o; o.r = mag * __cosf(t); o.i = mag * __sinf(t); return o;
}
__device__ __forceinline__ void put8(uint32_t a, uint32_t v) { sts16(a, v); sts16(a + 10, v); }
__device__ __forceinline__ void put4(uint32_t a, uint32_t v) { sts16(a, v); sts16(a + 6, v); }
__device__ __forceinline__ uint32_t sel4(int c, uint32_t a0, uint32_t a1, uint32_t a2, uint32_t a3) {
    return (uint32_t)((((uint64_t)(a2 | a3 << 16) << 32) | (a0 | a1 << 16)) >> (16 * c)) & 0xFFFFu;
}

struct KPrm { unsigned long long v[6]; uint32_t logdt, dskip; };
__device__ __forceinline__ void kload(const Params& p, KPrm& kp, int pos, int lane) {
    const int d = (pos & ~30) | ((pos & 6) << 2) | ((pos >> 2) & 6);
    const char* q = p.base + d * (NM * 2) + lane * 8;
#pragma unroll
    for (int k = 0; k < 6; k++) asm volatile("ld.global.nc.u64 %0, [%1];" : "=l"(kp.v[k]) : "l"(q + (long long)p.off[k] * 16));
    asm volatile("ld.global.nc.u16 %0, [%1];" : "=r"(kp.logdt) : "l"(p.base + (long long)p.off[6] * 16 + 2 * d));
    asm volatile("ld.global.nc.u16 %0, [%1];" : "=r"(kp.dskip) : "l"(p.base + (long long)p.off[7] * 16 + 2 * d));
}
template <class MID>
__device__ __forceinline__ void kgen(const KPrm& kp, int k0, bool fin, uint32_t scr, uint32_t ktab, MID mid) {
    const int lane = laneid(), g = lane >> 2, c = lane & 3;
    uint2 prm[6];
#pragma unroll
    for (int k = 0; k < 6; k++) { const uint64_t v = kp.v[k] >> (16 * k0); prm[k] = make_uint2((uint32_t)v, (uint32_t)(v >> 32)); }
    if (kp.logdt != 123456) STAMPW(4, 19);
    const float dt = rbf(expf(bflo(kp.logdt))), dsk = bflo(kp.dskip);
    float acc[2][3][4];
#pragma unroll
    for (int i = 0; i < 24; i++) (&acc[0][0][0])[i] = 0.f;
    const uint32_t la = scr + ((lane & 7) + 8 * ((lane >> 3) & 1)) * 144 + 16 * (lane >> 4);
    const uint32_t lb = scr + (32 + (lane & 7) + 8 * (lane >> 4)) * 144 + 16 * ((lane >> 3) & 1);
#pragma unroll 1
    for (int k = k0; k < (fin ? 4 : 1); k++) {
        {
        float v[6];
#pragma unroll
        for (int j = 0; j < 6; j++) { v[j] = bflo(prm[j].x); prm[j].x = prmt(prm[j].x, prm[j].y, 0x5432); prm[j].y >>= 16; }
        if (k == k0 && v[0] + v[1] + v[2] + v[3] + v[4] + v[5] != 123.456f) STAMPW(4, 15);
        const float e2 = (dt * v[0]) * 1.4426950408889634f, tn = (dt * v[1]) * 0.15915494309189535f;
        const cf z1 = cpow(e2, tn), z64 = cpow(e2 * 64.f, tn * 64.f);
        const cf z2 = cmul(z1, z1), z4 = cmul(z2, z2), z8 = cmul(z4, z4);
        const uint32_t st = scr + 4 * lane;
        auto put = [&](int row, cf v) { sts32(st + row * 144, pack(v.r, v.i)); };
        cf q[8];
        q[0].r = 1.f; q[0].i = 0.f; q[1] = z8; q[2] = cmul(z8, z8); q[3] = cmul(q[2], z8);
        q[4] = cmul(q[2], q[2]); q[5] = cmul(q[4], z8); q[6] = cmul(q[4], q[2]); q[7] = cmul(q[4], q[3]);
        const cf z128 = cmul(z64, z64), z192 = cmul(z128, z64), z256 = cmul(z128, z128), z512 = cmul(z256, z256), z1024 = cmul(z512, z512);
        put(0, q[0]); put(8, z64); put(16, z128); put(24, z192);
#pragma unroll
        for (int j = 1; j < 8; j++) { put(j, q[j]); put(8 + j, cmul(q[j], z64)); put(16 + j, cmul(q[j], z128)); put(24 + j, cmul(q[j], z192)); }
        cf pp[8];
        { const cf C = {v[4], -v[5]}, dB = {dt * v[2], dt * v[3]}; pp[0] = cmulc(C, dB); }
        pp[1] = cmulc(pp[0], z1); pp[2] = cmulc(pp[0], z2); pp[3] = cmulc(pp[1], z2);
#pragma unroll
        for (int j = 4; j < 8; j++) pp[j] = cmulc(pp[j - 4], z4);
#pragma unroll
        for (int j = 0; j < 8; j++) put(32 + j, pp[j]);
        const cf p256 = cmulc(pp[0], z256), p260 = cmulc(pp[4], z256), p512 = cmulc(pp[0], z512), p768 = cmulc(p256, z512), p1024 = cmulc(pp[0], z1024);
        put(40, p256); put(41, cmulc(pp[2], z256)); put(42, p260); put(43, cmulc(pp[6], z256));
        put(44, p512); put(45, cmulc(pp[4], z512)); put(46, p768); put(47, cmulc(p260, z512));
        put(48, p1024); put(49, cmulc(p256, z1024)); put(50, cmulc(p512, z1024)); put(51, cmulc(p768, z1024)); put(52, cmulc(p1024, z1024));
        __syncwarp();
#pragma unroll
        for (int ks = 0; ks < 128; ks += 32) {
            uint32_t a0[4], a1[4], b01[4], b2[2];
            ldsm4v(a0, la + ks); ldsm4v(a1, la + 16 * 144 + ks);
            ldsm4v(b01, lb + ks); ldsm2v(b2, lb + 16 * 144 + ks);
            mma(acc[0][0], a0[0], a0[1], a0[2], a0[3], b01[0], b01[1]);
            mma(acc[1][0], a1[0], a1[1], a1[2], a1[3], b01[0], b01[1]);
            mma(acc[0][1], a0[0], a0[1], a0[2], a0[3], b01[2], b01[3]);
            mma(acc[1][1], a1[0], a1[1], a1[2], a1[3], b01[2], b01[3]);
            mma(acc[0][2], a0[0], a0[1], a0[2], a0[3], b2[0], b2[1]);
            mma(acc[1][2], a1[0], a1[1], a1[2], a1[3], b2[0], b2[1]);
        }
        __syncwarp();
        }
        if (k == k0) { STAMPW(4, 26); mid(&acc[0][0][0]); }
    }
    if (!fin) return;
#pragma unroll
    for (int k = 0; k < 7; k++) if (k < 6 || lane < 8) sts128(ktab + 16 * lane + 512 * k, 0u, 0u, 0u, 0u);
    __syncwarp();
    if (lane == 0) acc[0][0][0] += dsk;
    const uint32_t kb = ktab + 8 * (6 + g);
    const uint32_t e0 = kb + sel4(c, PC, PA + 4, PC + 4, PA + 8), e1 = kb + sel4(c, PF, PB + 4, PF + 4, PB + 8);
    const uint32_t f0 = kb + sel4(c, PC + 256, PC + 260, PC + 512, PC + 768), f1 = kb + sel4(c, PA + 260, PA + 264, PC + 516, PC + 772);
    const uint32_t tx = ktab + TX + 4 * (14 + 64 * c + g);
#pragma unroll
    for (int i = 0; i < 4; i++) {
        const uint32_t v0 = pack(acc[i >> 1][0][2 * (i & 1)], acc[i >> 1][0][2 * (i & 1) + 1]);
        const uint32_t v1 = pack(acc[i >> 1][1][2 * (i & 1)], acc[i >> 1][1][2 * (i & 1) + 1]);
        const uint32_t v2 = pack(acc[i >> 1][2][2 * (i & 1)], acc[i >> 1][2][2 * (i & 1) + 1]);
        put8(e0 + 64 * i, v0); put8(e1 + 64 * i, v0 >> 16);
        put8(f0 + 64 * i, v1); put8(f1 + 64 * i, v1 >> 16);
        if (c < 2) put4(tx + 128 + 32 * i, v2 >> 16);
        if (i == 0) {
            if (c < 3) {
                put8(kb + sel4(c, PF + 256, PB + 260, PA + 516, 0), v1);
                if (g || c == 1) put8(kb + sel4(c, PB + 256, PF + 260, PA + 512, 0), v1);
            }
            if (lane == 0) { put8(kb + PC + 1024, v2); put8(kb + PC + 1028, v2); }
            else if (c < 2 || lane == 2) put4(tx, v2);
        } else if (c < 2) put4(tx + 32 * i, v2);
    }
    __syncwarp();
}

template <class WAIT, class FREE>
__device__ __forceinline__ void conv_prep(uint32_t umid, uint32_t ush, int sw, int w, int lane, int nb, WAIT wait_input, FREE free) {
    uint32_t o[3][4][4], e[4];
    const int u = lane & 7, half = (u ^ sw) & 1;
    const uint32_t a0 = (lane >> 3) * 1024 + (u << 4);
    if (w) {
        wait_input();
        const int dn = half ? 1024 : 0, dp = 12 - (half ? 0 : 1024);
#pragma unroll
        for (int s = 0; s < 3; s++) {
            const uint32_t a = umid + (a0 ^ (min(w - 1 + 3 * s, 7) * 144));
#pragma unroll
            for (int i = 0; i < 4; i++) {
                const uint4 v = lds128v(a + 4096 * i);
                o[s][i][1] = prmt(v.x, v.y, 0x5432); o[s][i][2] = prmt(v.y, v.z, 0x5432); o[s][i][3] = prmt(v.z, v.w, 0x5432);
                if (s < 2) {
                    uint32_t nx = lds32v((a ^ 16) + 4096 * i + dn);
                    if (i == 3 && lane >= 24 && half) nx = 0u;
                    (s ? e[i] : o[0][i][0]) = prmt(v.w, nx, 0x5432);
                }
                if (s > 0) {
                    uint32_t pv = lds32v((a ^ 16) + 4096 * i + dp);
                    if (i == 0 && lane < 8 && !half) pv = 0u;
                    o[s][i][0] = prmt(pv, v.x, 0x5432);
                }
            }
        }
        free();
#pragma unroll
        for (int i = 0; i < 4; i++) {
            sts128(ush + 16384 + (a0 ^ ((w - 1) * 144)) + 4096 * i, o[0][i][1], o[0][i][2], o[0][i][3], o[0][i][0]);
            sts128(ush + (a0 ^ ((w + 2) * 144)) + 4096 * i, o[1][i][0], o[1][i][1], o[1][i][2], o[1][i][3]);
            if (w < 3) sts128(ush + (a0 ^ ((w + 5) * 144)) + 4096 * i, o[2][i][0], o[2][i][1], o[2][i][2], o[2][i][3]);
            if (w == 1) sts128(ush + 16384 + (a0 ^ (3 * 144)) + 4096 * i, o[1][i][1], o[1][i][2], o[1][i][3], e[i]);
        }
    } else { free(); wait_input(); }
    const int ph = ((lane >> 2) - 1) & 3;
    const uint32_t t = lds16v(umid + ph * 128 + (((2 * w + sw) ^ ph) << 4));
    if (lane < 20) sts32(ush + 16384 + (4 + w) * 128 + 4 * lane, (lane >= 4 && (lane & 3) == 3) ? t << 16 : 0u);
    bar_sync(nb, 128);
}
__device__ __forceinline__ uint32_t urow(uint32_t umid, uint32_t ush, int phi, int unit) {
    return (phi < 0 ? ush : phi < 8 ? umid : ush + 16384) + (phi & 7) * 128 + ((unit ^ (phi & 7)) << 4);
}

template <class WAIT, class FREE>
__device__ __forceinline__ void conv(const Params& p, int pos, uint32_t umid, uint32_t ush, uint32_t ktab, uint32_t ebuf, int wg, int w, bool gate, WAIT wait_input, FREE free) {
    const int lane = laneid();
    const int g = lane >> 2, c = lane & 3, m = lane >> 3, rr = lane & 7, sw = (pos >> 2) & 1, unit = 2 * w + ((m ^ sw) & 1);
    const int o = g - 2 * c;
    const uint32_t tb = ktab + 8 * (6 + o), tx = ktab + TX + 4 * (14 + 2 * (g >> 1) + 8 * (g & 1) - 2 * c);
    uint32_t RA[9][2], RB[5][2], RC[17][2], RF[5][2], DG[2], ub[5];
#pragma unroll
    for (int j = 0; j < 17; j++) lds64v(RC[j], tb + PC + 64 * j);
#pragma unroll
    for (int j = 0; j < 9; j++) lds64v(RA[j], tb + PA + 64 * j);
#pragma unroll
    for (int j = 0; j < 5; j++) { lds64v(RB[j], tb + PB + 64 * j); lds64v(RF[j], tb + PF + 64 * j); }
    DG[0] = 0u;
    DG[1] = (RC[16][0] ^ 0x80008000u) & ((o == 0 ? 0xFFFFu : 0u) | (o == 1 ? 0xFFFF0000u : 0u));
#pragma unroll
    for (int pi = 0; pi < 4; pi++) ub[pi] = urow(umid, ush, rr + 2 - pi - 4 * (m >> 1), unit);
    ub[4] = urow(umid, ush, rr + 4 - (m >> 1), unit);
    conv_prep(umid, ush, sw, w, lane, NB_WG0 + wg, wait_input, free);
    float D[36][4];
    const float Z[4] = {0.f, 0.f, 0.f, 0.f};
    const uint32_t spec = ush + 16384 + (4 + w) * 128;
    const uint32_t ms = ebuf + (m >> 1) * 2816 + (m & 1) * 128 + rr * 16;
    uint32_t Q[5][4];
    ldsm4v(Q[0], spec + ((m == 1 && rr >= 6) ? 16 * (rr - 5) : 0));
    ldsm4v(Q[1], spec + ((m == 1 && rr == 7) ? 16 : 0));
    ldsm4v(Q[4], spec + (((m & 1) && rr + 4 - (m >> 1) >= 8) ? 16 * (rr - 3 - (m >> 1)) : 0));
    sts128(ms, 0u, 0u, 0u, 0u);
    uint32_t* y = reinterpret_cast<uint32_t*>(p.y + pos * S_) + lane;
    if (gate) bar_sync(NB_G1DONE, 256);
    STAMPW(4, 8);
    if (!gate) STAMPW(0, 25);
    const uint32_t ma = ebuf + (m & 1) * 256 + (m >> 1) * 128 + rr * 16;
    float E[2][4][4], O[4][4];
    uint32_t Bx[9][2], xq[4], xr[4];
#define X8L(q, pi, it) ldsm4v(q, ma + 256 * (it) + 2816 * (pi))
#define X8M(q, pi, it) do { _Pragma("unroll") for (int n = 3; n >= 0; n--) if ((it) <= 2 * n + 2) mmav(E[pi][n], q, Bx[(2 * n + 2 - (it)) < 0 ? 0 : 2 * n + 2 - (it)], (it) ? E[pi][n] : Z); } while (0)
#define X8(sl) do { if (k >= 8 && k < 12) { const int pi = (k - 8) >> 1 & 1, it = ((k & 1) * 5 + (sl)); \
        if (it == 0) { _Pragma("unroll") for (int j = 8; j >= 0; j--) { Bx[j][0] = lds32v(tx + 64 * j + 4 * pi); Bx[j][1] = lds32v(tx + 64 * j + 4 * pi - 32); } X8L(xq, pi, 0); } \
        else if (it <= 9) { if (it < 9) { if (it & 1) X8L(xr, pi, it); else X8L(xq, pi, it); } if (it & 1) X8M(xq, pi, it - 1); else X8M(xr, pi, it - 1); } } } while (0)
#define AT(dl) D[2 * k + (dl) + 2 > 35 ? 35 : 2 * k + (dl) + 2]
#define MM(q, R, dl) do { if (2 * k + (dl) >= -1 && 2 * k + (dl) < 32) mmav(AT(dl), q, R[dl], AT(dl)); } while (0)
#define MZ(q, R, dl) do { if (2 * k + (dl) >= -1 && 2 * k + (dl) < 32) mmav(AT(dl), q, R[dl], (k < 0 || (dl) >= 15) ? Z : AT(dl)); } while (0)
#pragma unroll
    for (int k = -1; k < 12; k++) {
        uint32_t S[4], C[2];
        if (k == 8) {
            STAMPW(4, 23);
            if (gate && w == 1) {
                const unsigned long long now = gtime();
                if (lane < NREP) asm volatile("red.relaxed.gpu.global.max.u64 [%0], %1;" :: "l"(p.cnt + C_T + CREP * lane), "l"(now + ((((unsigned)now - lds32v(SB + OFF_EP + 4)) * GATE2) >> 8)) : "memory");
                publish<false>(&p.cnt[C_S], lane);
            }
            __syncwarp();
        }
        MZ(Q[0], RA, 0); MZ(Q[0], RA, 1); MZ(Q[0], RA, 2);
        if (k >= 0) ldsm4v(Q[3], ub[3] + k * 1024);
        X8(0);
        MZ(Q[0], RA, 3); MZ(Q[0], RA, 4); MZ(Q[0], RA, 5); MZ(Q[0], RA, 6); MZ(Q[0], RA, 7); MZ(Q[0], RA, 8);
        X8(1);
        MM(Q[1], RB, 0); MM(Q[1], RB, 1); MM(Q[1], RB, 2); MM(Q[1], RB, 3); MM(Q[1], RB, 4);
        X8(2);
        if (k < 14) {
#pragma unroll
            for (int i = 0; i < 4; i++) S[i] = k < 0 ? Q[1][i] : hadd2(hadd2(Q[1][i], Q[3][i]), Q[2][i]);
        }
        if (k < 12) {
#pragma unroll
            for (int h = 0; h < 2; h++) C[h] = k < 0 ? Q[0][h] : hadd2(Q[0][h], Q[0][2 + h]);
        }
        uint32_t a7[2], a9[2];
        if (k < 8) {
#pragma unroll
            for (int h = 0; h < 2; h++) { a7[h] = k < 0 ? Q[4][2 + h] : hadd2(Q[4][2 + h], Q[1][2 + h]); a9[h] = k < 0 ? Q[4][h] : hadd2(Q[4][h], Q[2][2 + h]); }
        }
        MM(S, RC, 5); MM(S, RC, 6); MM(S, RC, 7); MM(S, RC, 8);
        if (k < 15) ldsm4v(Q[0], ub[0] + (k + 1) * 1024);
        if (k >= 0) { MM(Q[2], RC, 0); MM(Q[2], RC, 1); MM(Q[2], RC, 2); }
        if (k < 15) ldsm4v(Q[1], ub[1] + (k + 1) * 1024);
        if (k < 7) ldsm4v(Q[4], ub[4] + (k + 1) * 1024);
        if (k >= 0) { MM(Q[2], RC, 3); MM(Q[2], RC, 4); }
        if (k < 12) { S[0] = hadd2(S[0], C[0]); S[1] = hadd2(S[1], C[1]); }
        if (k < 8) {
            uint32_t mx[4];
#pragma unroll
            for (int h = 0; h < 2; h++) { const uint32_t n7 = hadd2(S[h], a7[h]), n9 = hadd2(n7, a9[h]); mx[h] = prmt(n9, n7, 0x7610); mx[2 + h] = prmt(n7, n9, 0x7610); }
            stsm4(ms + (k + 2) * 256, mx);
        }
        if (k < 15) ldsm4v(Q[2], ub[2] + (k + 1) * 1024);
        X8(3);
        if (k >= 0) { MM(Q[3], RF, 0); MM(Q[3], RF, 1); }
        MZ(S, RC, 16);
        if (k >= 0) { MM(Q[3], RF, 2); MM(Q[3], RF, 3); MM(Q[3], RF, 4); }
        MZ(S, RC, 9); MZ(S, RC, 10); MZ(S, RC, 11); MZ(S, RC, 12); MZ(S, RC, 13); MZ(S, RC, 14); MZ(S, RC, 15);
        X8(4);
        if (k >= 0 && k < 8) mmav(AT(16), Q[3], DG, AT(16));
        if (k >= 0) {
            float v0 = AT(0)[0] + AT(-1)[2], v1 = AT(0)[1] + AT(-1)[3], v2 = AT(0)[2] + AT(1)[0], v3 = AT(0)[3] + AT(1)[1];
            if (k >= 8) { O[k & 3][0] = v0; O[k & 3][1] = v1; O[k & 3][2] = v2; O[k & 3][3] = v3; }
            else { y[64 * k] = movm(pack(v0, v1)); y[64 * k + 32] = movm(pack(v2, v3)); }
        }
    }
#pragma unroll
    for (int k = 8; k < 12; k++) {
        const int n = (k - 8) >> 1, h = 2 * (k & 1);
        y[64 * k] = movm(pack(O[k & 3][0] + E[0][n][h], O[k & 3][1] + E[1][n][h])); y[64 * k + 32] = movm(pack(O[k & 3][2] + E[0][n][h + 1], O[k & 3][3] + E[1][n][h + 1]));
    }
    {
        uint32_t T[4][4][4], S[2][4];
#pragma unroll
        for (int i = 0; i < 4; i++) { T[0][0][i] = Q[0][i]; T[0][1][i] = Q[1][i]; T[0][2][i] = Q[2][i]; }
        ldsm4v(T[0][3], ub[3] + 12 * 1024);
#pragma unroll
        for (int k = 13; k < 16; k++)
#pragma unroll
            for (int pi = 0; pi < 4; pi++) ldsm4v(T[k - 12][pi], ub[pi] + k * 1024);
#pragma unroll
        for (int dl = 0; dl < 8; dl++)
#pragma unroll
            for (int k = 12; k < 16; k++) MM(T[k - 12][0], RA, dl);
#pragma unroll
        for (int k = 0; k < 2; k++)
#pragma unroll
            for (int i = 0; i < 4; i++) S[k][i] = hadd2(hadd2(T[k][1][i], T[k][3][i]), T[k][2][i]);
#pragma unroll
        for (int dl = 0; dl < 5; dl++)
#pragma unroll
            for (int k = 12; k < 16; k++) MM(T[k - 12][1], RB, dl);
#pragma unroll
        for (int dl = 0; dl < 8; dl++)
#pragma unroll
            for (int k = 12; k < 16; k++) { if (dl < 5) MM(T[k - 12][2], RC, dl); else if (k < 14) MM(S[k - 12], RC, dl); }
#pragma unroll
        for (int dl = 0; dl < 5; dl++)
#pragma unroll
            for (int k = 12; k < 16; k++) MM(T[k - 12][3], RF, dl);
#pragma unroll
        for (int k = 12; k < 16; k++) {
            const float2 e0 = make_float2(E[0][(k - 8) >> 1][2 * (k & 1)], E[0][(k - 8) >> 1][2 * (k & 1) + 1]), e1 = make_float2(E[1][(k - 8) >> 1][2 * (k & 1)], E[1][(k - 8) >> 1][2 * (k & 1) + 1]);
            y[64 * k] = movm(pack(AT(0)[0] + AT(-1)[2] + e0.x, AT(0)[1] + AT(-1)[3] + e1.x));
            y[64 * k + 32] = movm(pack(AT(0)[2] + AT(1)[0] + e0.y, AT(0)[3] + AT(1)[1] + e1.y));
        }
    }
#undef AT
#undef MM
#undef MZ
    STAMPW(4, 24);
    if (!gate) STAMPW(0, 29);
}

__device__ __forceinline__ float gelu2x(float v) {
    float t; const float u = v * fmaf(v * v, 0.044715f * 0.7978845608028654f, 0.7978845608028654f);
    asm("tanh.approx.f32 %0, %1;" : "=f"(t) : "f"(u));
    return fmaf(v, t, v);
}

struct Maps { CUtensorMap w[2], act[2], u, y, xr, w1big; };

__global__ void __launch_bounds__(NTHR, 1) fused_kernel(const __grid_constant__ Params p, const __grid_constant__ Maps mp) {
    extern __shared__ __align__(1024) uint8_t smem[];
    constexpr uint32_t sb = SB, bars = sb + OFF_BAR, slots = sb + OFF_SLOT;
    const int bid = blockIdx.x, lane = threadIdx.x & 31;
    STAMPINIT();
    STAMPG(1, 31);
    STAMPW(0, 0);
    KPrm kp;
    kload(p, kp, bid < N_G1 ? 4 * bid + ((threadIdx.x >> 5) & 3) : (bid < N_G2 ? 8 * bid - 432 : 12 * bid - 944) + (threadIdx.x >> 5), lane);
    STAMPW(4, 14);
    const int warp = __shfl_sync(0xffffffffu, threadIdx.x >> 5, 0);
    const int wg = warp >> 2, w = warp & 3;
    const bool g1 = bid < N_G1, g2 = bid < N_G2;
    const int dt = bid & 3, mt = bid >> 2;
    const bool cw = wg == 1 || !g1;
    const bool two = !g2 && wg == 0;
    const int pos = (g1 ? 4 * bid + w : (g2 ? 432 + 8 * (bid - N_G1) : 592 + 12 * (bid - N_G2)) + warp);
    const bool el = elect();
    const uint32_t stg = g1 ? slots + 4 * SLOT + ABYTES : slots;
    if (warp == 3 && el) {
#pragma unroll
        for (int i = 0; i <= B_DUMMY; i++) mbar_init(bars + 8 * i, 1);
        asm volatile("fence.mbarrier_init.release.cluster;" ::: "memory");
    }
    __syncwarp();
    uint32_t bias;
    asm volatile("ld.global.nc.u16 %0, [%1];" : "=r"(bias) : "l"(((w & 2) ? p.b2 : p.b1) + (((w & 2) ? g2 : g1) ? mt * 64 + (threadIdx.x & 63) : 0)));
    auto cntr = [&](int i) { unsigned b; asm volatile("mov.u32 %0, %%ctaid.x;" : "=r"(b)); return p.cnt + (CREP * (b % NREP) + i); };
    unsigned ep0 = ld_relaxed(cntr(C_Y + pos / 160 + (lane & p.zero)));
    auto poll = [&](const unsigned* ptr, unsigned per_launch, unsigned pause = 0) {
        const unsigned target = lds32v(sb + OFF_EP) * per_launch;
        int it = SPIN_LIMIT;
#pragma unroll 1
        do { --it; if (pause) __nanosleep(pause); } while (__ballot_sync(0xffffffffu, (int)(ld_relaxed(ptr) - target) < 0 && it > 0));
        if (it <= 0) __trap();
        fence_async_global();
    };
    auto load_w = [&](int ph2, int kb, int slot) {
        mbar_expect_tx(bars + 8 * slot, SLOT);
        tma3d(slots + slot * SLOT, &mp.w[ph2], mt * 64, kb >> 2, (kb & 3) * 64, bars + 8 * slot);
    };
    auto load_a = [&](int ph2, int kb, int slot) { tma3d(slots + slot * SLOT + ABYTES, &mp.act[ph2], 0, dt * 40, kb * 4, bars + 8 * slot); };
    auto load_u = [&](uint32_t dst, int grp, int bar) { mbar_expect_tx(bars + 8 * (B_U + bar), 16384); tma4d(dst, &mp.u, 0, grp, bars + 8 * (B_U + bar)); };
    if (warp == 3 && g2 && el) {
        const long long c0 = clock64();
        while (clock64() - c0 < XDELAY) { }
        mbar_expect_tx(bars + 8 * B_X, 16 * 1280);
        tma4d(stg, &mp.xr, bid >> 4, 16 * (bid & 15), bars + 8 * B_X);
        if (WEARLY && g1) {
#pragma unroll 1
            for (int i = 0; i < 6; i++) load_w(0, i, i);
        }
    }
    __syncwarp();
    uint32_t umid, ush, ktab, scr, ebuf;
    if (g1) {
        umid = sb + OFF_X; ush = slots + 4 * SLOT; ktab = umid + 16384 + w * KTAB; ebuf = ush + 32768 + w * 5632;
        scr = wg == 0 ? slots + w * SLOT + ABYTES : w ? slots + 6 * SLOT + (w - 1) * 9216 : umid;
    } else { ush = slots + wg * 49152; umid = ush + 32768; scr = slots + 98304 + warp * (9216 + 2 * KTAB); ebuf = scr; ktab = scr + 9216; }

#pragma unroll 1
    for (int round = 0;; round++) {
    kgen(kp, g1 ? wg : 0, cw, scr, ktab + round * KTAB, [&](float* acc) {
        const uint32_t xch = slots + w * SLOT + ABYTES + 9216 + 16 * laneid();
        if (!cw)
#pragma unroll
            for (int j = 0; j < 6; j++) sts128(xch + 512 * j, __float_as_uint(acc[4 * j]), __float_as_uint(acc[4 * j + 1]), __float_as_uint(acc[4 * j + 2]), __float_as_uint(acc[4 * j + 3]));
        if (wg == 0) sts32(sb + OFF_BIAS + 4 * threadIdx.x, __float_as_uint(bflo(bias) * ((w & 2) ? 2.f : 1.f)));
        if (warp == 0 && round == 0) sts32(sb + OFF_EP, ep0 / 40u + 1u);
        if (round == 0) __syncthreads();
        if (g1 && warp >= 6 && el) {
            if (warp == 6 && dt < PFN) pf3d(&mp.w1big, mt * 64, dt + 1, 0);
            if (!WEARLY) { load_w(0, warp - 6, warp - 6); load_w(0, warp - 4, warp - 4); load_w(0, warp - 2, warp - 2); }
        }
        __syncwarp();
        if (g2) layernorm(p, stg, bid, warp, el);
        if (g1 && wg) {
#pragma unroll
            for (int j = 0; j < 6; j++) {
                const uint4 v = lds128v(xch + 512 * j);
                acc[4 * j] += __uint_as_float(v.x); acc[4 * j + 1] += __uint_as_float(v.y); acc[4 * j + 2] += __uint_as_float(v.z); acc[4 * j + 3] += __uint_as_float(v.w);
            }
            fence_async_smem();
            bar_arrive(NB_XCH, 160);
        }
    });
    if (!two || round) break;
    kload(p, kp, pos + 8, laneid());
    }
    STAMPW(0, 4);
    STAMPW(4, 5);
    if (g1) {
        if (wg) {
            fence_async_smem();
            bar_sync(NB_KGEN, 256);
            if (w == 0) { fence_async_global(); if (el) { load_w(0, 6, 6); load_a(0, 6, 6); load_u(umid, bid, 1); } __syncwarp(); STAMPW(4, 25); }
        } else if (w == 1) {
            bar_sync(NB_XCH, 160);
            STAMPW(1, 20);
            poll(cntr(C_H + (lane >> 1)), 8u);
            STAMPW(1, 22);
            if (el) {
#pragma unroll
                for (int i = 0; i < 6; i++) load_a(0, i, i);
            }
            __syncwarp();
            STAMPW(1, 1);
        }
        if (!wg) bar_sync(NB_KGEN, 256);
    } else {
        if (w == 0) { poll(cntr(C_H + (lane >> 1)), 8u); if (el) load_u(umid, pos >> 2, wg); STAMPW(4, 1); }
        if (warp == 7 && g2 && el)
#pragma unroll 1
            for (int k = dt; k < 27; k += 4) pf3d(&mp.w[1], mt * 64, k >> 2, (k & 3) * 64);
        __syncwarp();
    }
    int slot = 0; uint32_t ph = 0;
#pragma unroll 1
    for (int ph2 = 0; ph2 < 2; ph2++) {
        if (ph2 && cw) {
#pragma unroll 1
            for (int i = 0; i <= (int)two; i++) {
                conv(p, pos + 8 * i, umid, ush, ktab + i * KTAB, ebuf, wg, w, g1, [&]() {
                    mbar_wait(bars + 8 * (B_U + wg), i);
                }, [&]() {
            if (g1 && w == 0) {
                int ps = 0; uint32_t pp = 0;
#pragma unroll 1
                for (int j = 7; j < 32; j++) {
                    mbar_wait(bars + 8 * (B_EMPTY + ps), pp);
                    if (el) {
                        load_w(0, j, ps); load_a(0, j, ps);
                        const int k = j + 4 * PFN - 3;
                        if ((k & 3) == dt) {
                            if (k < 32) pf3d(&mp.w[0], mt * 64, k >> 2, dt * 64);
                            if (j >= 8) { pf3d(&mp.w[1], mt * 64, (j - 8) >> 2, dt * 64); if (j >= 28) pf3d(&mp.w[1], mt * 64, 6, min(dt, 2) * 64); }
                        }
                    }
                    __syncwarp();
                    if (++ps == NSLOT) { ps = 0; pp ^= 1; }
                }
                mbar_wait(bars + 8 * (B_EMPTY + 4), 1); mbar_wait(bars + 8 * (B_EMPTY + 5), 1);
                if (lane >= 4 && lane < 7) { mbar_arrive(bars + 8 * lane); mbar_arrive(bars + 8 * (B_EMPTY + lane)); }
                __syncwarp();
            }
                    if (g1) bar_sync(NB_WG1, 128);
                });
                fence_async_smem();
                if (g2) { if (wg) bar_arrive(NB_CONVDONE, 256); else bar_sync(NB_CONVDONE, 256); }
                if (g1) {
                    if (w) bar_arrive(NB_GOK, 160);
                    else {
                        bar_sync(NB_GOK, 160);
                        fence_async_global();
                        if (el) { load_w(1, 4, 4); load_a(1, 4, 4); load_w(1, 5, 5); load_a(1, 5, 5); }
                    }
                }
                fence_async_global();
                bar_sync(NB_WG0 + wg, 128);
                if (i < (int)two && w == 0 && el) load_u(umid, (pos >> 2) + 2, 0);
                __syncwarp();
                if (w == 1) publish<true>(&p.cnt[C_Y + (pos + 8 * i) / 160], lane);
            }
            STAMPW(4, 9);
        }
        if (warp == 4 && ph2 && g2) {
            int ps = 0; uint32_t pp = g1;
#pragma unroll 1
            for (int j = 7; j < 27; j++) {
                mbar_wait(bars + 8 * (B_EMPTY + ps), pp);
                if (j == 7) fence_async_global();
                if (el) { load_w(1, j, ps); load_a(1, j, ps); }
                __syncwarp();
                if (++ps == NSLOT) { ps = 0; pp ^= 1; }
            }
        }
        if (wg == 1 && ph2 && g2) {
            if (w == 3) {
                poll(cntr(C_Y + dt), 40u, 200);
                if (el) { mbar_expect_tx(bars + 8 * B_Y, 20480); tma2d(sb + OFF_X, &mp.y, mt * 64, dt * 160, bars + 8 * B_Y); }
                __syncwarp();
                STAMPW(7, 3);
            }
            {
                const int v = w;
                const int lane = laneid(), g = lane >> 2, m = lane >> 3, rr = lane & 7;
                const uint4* px = reinterpret_cast<const uint4*>(p.x + (mt * 64 + 16 * v + g) * D_ + dt * 160) + (lane & 3);
                uint4 xr[10];
#pragma unroll
                for (int j = 0; j < 10; j++) xr[j] = __ldg(px + (j & 1) * D_ + (j >> 1) * 4);
                const uint32_t ya = sb + OFF_X + (8 * (m >> 1) + rr) * 128 + (((2 * v + (m & 1)) ^ rr) << 4);
                mbar_wait(bars + 8 * B_Y, 0);
#pragma unroll
                for (int j = 0; j < 5; j++) {
                    uint32_t y0[4], y1[4];
                    ldsm4tv(y0, ya + j * 4096);
                    ldsm4tv(y1, ya + j * 4096 + 2048);
#pragma unroll
                    for (int h = 0; h < 2; h++) {
                        const uint4 xv = xr[2 * j + h];
                        sts128(ya + j * 4096 + h * 2048, hadd2(xv.x, y0[h]), hadd2(xv.y, y0[2 + h]), hadd2(xv.z, y1[h]), hadd2(xv.w, y1[2 + h]));
                    }
                }
            }
            bar_arrive(NB_RES, 256);
        }
        if (wg == 0 && (ph2 ? g2 : g1)) {
            if (ph2) {
                if (w == 0) {
                    if (el) {
                        load_w(1, 6, 6);
                        if (!g1)
#pragma unroll 1
                            for (int i = 0; i < 6; i++) load_w(1, i, i);
                    }
                    const unsigned* ptr = cntr(lane < 4 ? C_G + lane : lane == 4 ? C_S : lane == 5 ? C_TG : C_T);
                    const unsigned target = lds32v(sb + OFF_EP) * 108u;
                    unsigned v, pend; int it = 0;
#pragma unroll 1
                    do { v = ld_relaxed(ptr); pend = __ballot_sync(0xffffffffu, lane < 5 && (int)(v - target) < 0); if (++it > SPIN_LIMIT) __trap(); } while (pend & 15);
                    fence_async_global();
                    const unsigned tg = __shfl_sync(0xffffffffu, v, 5);
#pragma unroll 1
                    for (it = 0; it < 400 && (int)((unsigned)gtime() - tg) < GATE1; it++) { }
                    STAMPW(0, 2);
                    if (el) {
                        load_a(1, 0, 0); load_a(1, 1, 1); load_a(1, 2, 2); load_a(1, 3, 3); load_a(1, 6, 6);
                        if (!g1) { load_a(1, 4, 4); load_a(1, 5, 5); }
                    }
                    if (g1) bar_arrive(NB_GOK, 160);
#pragma unroll 1
                    while (pend) { v = ld_relaxed(ptr); pend = __ballot_sync(0xffffffffu, lane < 5 && (int)(v - target) < 0); if (++it > SPIN_LIMIT) __trap(); }
                    v = __shfl_sync(0xffffffffu, v, 6);
#pragma unroll 1
                    for (it = 0; it < 400 && (int)((unsigned)gtime() - v) < 0; it++) { }
                }
                if (g1) bar_sync(NB_CONVDONE, 256);
                STAMPW(0, 10);
            }
            float acc[80];
            {
                const uint32_t ba = sb + OFF_BIAS + 4 * (64 * ph2 + 16 * w + (laneid() >> 2));
                const float b0 = __uint_as_float(lds32v(ba)), b1 = __uint_as_float(lds32v(ba + 32));
#pragma unroll
                for (int i = 0; i < 80; i++) acc[i] = (i & 2) ? b1 : b0;
            }
            uint32_t rel = bars + 8 * B_DUMMY;
            const int n = ph2 ? 27 : 32;
#pragma unroll 1
            for (int i = n; i > 0; i--) {
                mbar_wait(bars + 8 * slot, ph);
                if (i == n) STAMPW(0, 27 + ph2);
                if (i == 26 && !ph2) STAMPW(0, 29);
                const uint32_t lo = (slots >> 4) + slot * (SLOT / 16);
                const uint64_t da = 0x4000004002000000ull | lo, db = 0xC000001000010000ull | (lo + ABYTES / 16);
                wg_fence();
#pragma unroll
                for (int k = 0; k < 4; k++) wgmma_n160(acc, da + k * 128, db + k * 320);
                wg_commit();
                wg_wait<1>();
                if (threadIdx.x == 0) mbar_arrive(rel);
                rel = bars + 8 * (B_EMPTY + slot);
                if (++slot == NSLOT) { slot = 0; ph ^= 1; }
            }
            wg_wait<0>();
            if (ph2 == 0) { if (w == 2) sts32(sb + OFF_EP + 4, (unsigned)gtime()); bar_arrive(NB_G1DONE, 256); }
            STAMPW(0, ph2 ? 11 : 6);
            const int lane = laneid(), g = lane >> 2, c = lane & 3, m = lane >> 3, rr = lane & 7;
            if (ph2 == 0) {
                const uint32_t gb = slots + 6 * SLOT + w * 5120;
#pragma unroll
                for (int j = 0; j < 10; j++) {
                    uint32_t P[4];
#pragma unroll
                    for (int i = 0; i < 4; i++) P[i] = pack(gelu2x(acc[8 * j + 2 * i]), gelu2x(acc[8 * j + 2 * i + 1]));
                    stsm4t(gb + (8 * (m >> 1) + rr) * 32 + (((m ^ (rr >> 2)) & 1) << 4) + j * 512, P);
                }
                fence_async_smem();
                __syncwarp();
                STAMPW(0, 21);
                if (el) { bulk_store<5120>(p.G + ((4 * mt + w) * D_ + dt * 160) * 16, gb); bulk_wait(); }
                __syncwarp();
                if (lane < NREP) asm volatile("red.relaxed.gpu.global.max.u64 [%0], %1;" :: "l"(p.cnt + C_TG + CREP * lane), "l"(gtime()) : "memory");
                publish<false>(&p.cnt[C_G + dt], lane);
                if (el) { load_w(1, w, w); if (w == 3) mbar_arrive(rel); }
                bar_sync(NB_WG0, 128);
                STAMPW(1, 7);
                slot = 0; ph = 1;
            } else {
                uint32_t P[40];
#pragma unroll
                for (int j = 0; j < 40; j++) P[j] = packv(acc[2 * j], acc[2 * j + 1]);
                uint4* o = reinterpret_cast<uint4*>(p.out + (mt * 64 + 16 * w + g) * D_ + dt * 160) + c;
                const uint32_t ra = sb + OFF_X + (8 * (m >> 1) + rr) * 128 + (((2 * w + (m & 1)) ^ rr) << 4);
                bar_sync(NB_RES, 256);
#pragma unroll
                for (int j = 0; j < 10; j++) {
                    const int a0 = 8 * (j >> 1) + (j & 1);
                    const uint4 r = lds128v(ra + j * 2048);
                    o[(j & 1) * D_ + 4 * (j >> 1)] = make_uint4(hfma2(P[a0], 0x3F003F00u, r.x), hfma2(P[a0 + 2], 0x3F003F00u, r.y), hfma2(P[a0 + 4], 0x3F003F00u, r.z), hfma2(P[a0 + 6], 0x3F003F00u, r.w));
                }
                STAMPW(0, 12);
                STAMPG(0, 30);
            }
        }
    }
    if ((uint32_t)__cvta_generic_to_shared(smem) != sb) __trap();
    STAMPDUMP();
}

typedef CUresult (*EncFn)(CUtensorMap*, CUtensorMapDataType, cuuint32_t, void*, const cuuint64_t*, const cuuint64_t*, const cuuint32_t*,
                          const cuuint32_t*, CUtensorMapInterleave, CUtensorMapSwizzle, CUtensorMapL2promotion, CUtensorMapFloatOOBfill);

CUtensorMap make_map(EncFn enc, const void* ptr, int rank, const cuuint64_t* dims, const cuuint64_t* strides, const cuuint32_t* box, bool swz = true) {
    CUtensorMap m; cuuint32_t es[4] = {1, 1, 1, 1};
    CUresult r = enc(&m, CU_TENSOR_MAP_DATA_TYPE_BFLOAT16, rank, const_cast<void*>(ptr), dims, strides, box, es, CU_TENSOR_MAP_INTERLEAVE_NONE,
        swz ? CU_TENSOR_MAP_SWIZZLE_128B : CU_TENSOR_MAP_SWIZZLE_NONE, PROMO, CU_TENSOR_MAP_FLOAT_OOB_FILL_NONE);
    if (r != CUDA_SUCCESS) fprintf(stderr, "cuTensorMapEncodeTiled failed: %d\n", (int)r);
    return m;
}

}

extern "C" void kernel_launch(void* const* d_in, const int* in_sizes, int n_in, void* d_out, int out_size) {
    (void)in_sizes; (void)n_in; (void)out_size;
    typedef const __nv_bfloat16* bp;
    Params p;
    p.x = (bp)d_in[0];
    p.base = (const char*)d_in[1];
    for (int i = 0; i < 8; i++) p.off[i] = (int)(((const char*)d_in[1 + i] - p.base) / 16);
    p.b1 = (bp)d_in[11]; p.b2 = (bp)d_in[13]; p.out = (__nv_bfloat16*)d_out; p.zero = 0;
    EncFn enc = nullptr; cudaDriverEntryPointQueryResult q;
    cudaGetDriverEntryPoint("cuTensorMapEncodeTiled", (void**)&enc, cudaEnableDefault, &q);
    cudaGetSymbolAddress((void**)&p.uh, g_uh); cudaGetSymbolAddress((void**)&p.G, g_G);
    cudaGetSymbolAddress((void**)&p.y, g_y); cudaGetSymbolAddress((void**)&p.cnt, g_cnt);
    Maps mp;
    { cuuint64_t d[3] = {F_, 8, 256}, s[2] = {F_ * 2, F_ * 16}; cuuint32_t b[3] = {64, 1, 64}; mp.w[0] = make_map(enc, d_in[10], 3, d, s, b);
      b[2] = 256; mp.w1big = make_map(enc, d_in[10], 3, d, s, b); }
    { cuuint64_t d[3] = {S_, 7, 256}, s[2] = {S_ * 512, S_ * 2}; cuuint32_t b[3] = {64, 1, 64}; mp.w[1] = make_map(enc, d_in[12], 3, d, s, b); }
    { cuuint64_t d[3] = {64, 160, 128}, s[2] = {128, D_ * 32}; cuuint32_t b[3] = {64, 40, 4};
      mp.act[0] = make_map(enc, p.uh + D_ * S_, 3, d, s, b, false); d[2] = F_ / 16; mp.act[1] = make_map(enc, p.G, 3, d, s, b, false); }
    { cuuint64_t d[2] = {S_, D_}, s[1] = {S_ * 2}; cuuint32_t b[2] = {64, 160}; mp.y = make_map(enc, p.y, 2, d, s, b); }
    { cuuint64_t d[4] = {160, 4, 8, 256}, s[3] = {320, D_ * 2, D_ * 16}; cuuint32_t b[4] = {160, 4, 1, 16}; mp.xr = make_map(enc, p.x, 4, d, s, b, false); }
    { cuuint64_t d[4] = {64, 8, 16, 160}, s[3] = {16 * D_ * 32, D_ * 32, 128}; cuuint32_t b[4] = {64, 8, 16, 1}; mp.u = make_map(enc, p.uh, 4, d, s, b); }
    cudaFuncSetAttribute(fused_kernel, cudaFuncAttributeMaxDynamicSharedMemorySize, SMEM_BYTES);
    fused_kernel<<<NCTA, NTHR, SMEM_BYTES, cudaStreamPerThread>>>(p, mp);
}
```
